```python
import torch

def _softmax(x, axis=-1):
    return torch.softmax(x, dim=axis)
def _gelu(x):
    return torch.nn.functional.gelu(x, approximate="tanh")
def _silu(x):
    return torch.nn.functional.silu(x)
def _sigmoid(x):
    return torch.sigmoid(x)
def _layernorm(x, axis=-1, eps=1e-5):
    m = x.mean(dim=axis, keepdim=True)
    v = x.var(dim=axis, keepdim=True, unbiased=False)
    return (x - m) / torch.sqrt(v + eps)
def _scatter_add(tgt, idx, src, axis=0):
    return tgt.clone().index_add_(axis, idx, src)
def _segment_sum(src, seg, n):
    out = torch.zeros((n,) + src.shape[1:], dtype=src.dtype)
    return out.index_add_(0, seg, src)
def _pad(x, pw):
    flat = tuple(v for pair in reversed(pw) for v in pair)
    return torch.nn.functional.pad(x, flat)

kernel_name = 'standalone__self_sup_conv_stem_wavlm__speech'

def setup_inputs():

    _w = (lambda a: (lambda t: t.to(torch.bfloat16) if t.is_floating_point() else t)(torch.as_tensor(a)))
    B, T, D, K = 2, 16000, 256, 3
    scale = (K * D) ** -0.5
    return {
        "x": _w((lambda *s: torch.randn(*s, dtype=torch.bfloat16) * 0.05)(B, T, D)),
        "w": _w((lambda *s: torch.randn(*s, dtype=torch.bfloat16) * 0.05)(K, D, D) * scale),
        "gn_gamma": _w((lambda *s: torch.randn(*s, dtype=torch.bfloat16) * 0.05)(D) * 0.1 + 1.0),
        "gn_beta": _w((lambda *s: torch.randn(*s, dtype=torch.bfloat16) * 0.05)(D) * 0.1),
    }

def reference(x, w, gn_gamma, gn_beta):
    B, T, D = x.shape
    K = w.shape[0]
    s = 2
    L = (T - K) // s + 1
    h = torch.einsum('blc,cd->bld', x[:, 0:s * L:s, :], w[0])
    for i in range(1, K):
        h = h + torch.einsum('blc,cd->bld', x[:, i:i + s * L:s, :], w[i])
    mu = torch.einsum('bld->bd', h)[:, None, :] / L
    var = torch.einsum('bld->bd', (h - mu) ** 2)[:, None, :] / L
    h = (h - mu) / torch.sqrt(var + 1e-5)
    h = h * gn_gamma[None, None, :] + gn_beta[None, None, :]
    return _gelu(h)
```

```cpp
#include <cuda_runtime.h>
#include <cuda_bf16.h>
#include <cuda.h>
#include <stdint.h>

#define EVICT 1
#define NCHUNK 4
#define STAG0 5
#define STAG1 99
#define P1 2400u
#define P2 3600u
#define P3 5200u

namespace {

constexpr int kT = 16000, kD = 256, kL = 7999;
constexpr int kTilesPerBatch = 32;
constexpr int kXSlot = 33792;
constexpr int kXSlots = 4;
constexpr int kWStage = 16384;
constexpr int kWStages = 5;
constexpr int kOffW = kXSlots * kXSlot;
constexpr int kOffBar = kOffW + kWStages * kWStage;
constexpr int kSmemBytes = kOffBar + 256;
constexpr int kThreads = 288;
constexpr uint32_t kSpinLimit = 1u << 26;

struct Sync {
  float4 stats[2][2][256];
  unsigned epoch[2][16];
};
__device__ Sync g_sync;
#define TSTAMP(k)
#define TSTAMPB(k)
#define CSTAMP(k)

__device__ __forceinline__ uint32_t smem_u32(const void* p) { return (uint32_t)__cvta_generic_to_shared(p); }
__device__ __forceinline__ void mbar_init(uint32_t bar, uint32_t cnt) {
  asm volatile("mbarrier.init.shared::cta.b64 [%0], %1;" ::"r"(bar), "r"(cnt) : "memory");
}
__device__ __forceinline__ void mbar_expect_tx(uint32_t bar, uint32_t bytes) {
  asm volatile("mbarrier.arrive.expect_tx.shared::cta.b64 _, [%0], %1;" ::"r"(bar), "r"(bytes) : "memory");
}
__device__ __forceinline__ void mbar_wait(uint32_t bar, uint32_t parity) {
  uint32_t done, it = 0;
  do {
    asm volatile(
        "{\n\t.reg .pred p;\n\t"
        "mbarrier.try_wait.parity.shared::cta.b64 p, [%1], %2;\n\t"
        "selp.u32 %0, 1, 0, p;\n\t}"
        : "=r"(done) : "r"(bar), "r"(parity) : "memory");
    if (++it > kSpinLimit) __trap();
  } while (!done);
}
__device__ __forceinline__ void mbar_arrive(uint32_t bar) {
  asm volatile("mbarrier.arrive.shared::cta.b64 _, [%0];" ::"r"(bar) : "memory");
}
__device__ __forceinline__ void tma_load3(uint32_t dst, const CUtensorMap* tm, int c0, int c1, int c2, uint32_t bar) {
  asm volatile(
      "cp.async.bulk.tensor.3d.shared::cluster.global.mbarrier::complete_tx::bytes "
      "[%0], [%1, {%3, %4, %5}], [%2];"
      ::"r"(dst), "l"(tm), "r"(bar), "r"(c0), "r"(c1), "r"(c2) : "memory");
}
__device__ __forceinline__ void tma_store3(const CUtensorMap* tm, uint32_t src, int c0, int c1, int c2) {
  uint64_t pol;
  asm volatile("createpolicy.fractional.L2::evict_first.b64 %0, 1.0;" : "=l"(pol));
  asm volatile("cp.async.bulk.tensor.3d.global.shared::cta.bulk_group.L2::cache_hint [%0, {%2, %3, %4}], [%1], %5;"
               ::"l"(tm), "r"(src), "r"(c0), "r"(c1), "r"(c2), "l"(pol) : "memory");
}
__device__ __forceinline__ uint64_t make_desc(uint32_t addr) {
  return (uint64_t)((addr & 0x3FFFF) >> 4) | ((uint64_t)64 << 16) | ((uint64_t)64 << 32) | ((uint64_t)1 << 62);
}

#define ACC8(o) "+f"(d[o]), "+f"(d[o + 1]), "+f"(d[o + 2]), "+f"(d[o + 3]), "+f"(d[o + 4]), "+f"(d[o + 5]), "+f"(d[o + 6]), "+f"(d[o + 7])
#define ACC32(o) ACC8(o), ACC8(o + 8), ACC8(o + 16), ACC8(o + 24)
__device__ __forceinline__ void wgmma_m64n256k16(float (&d)[128], uint64_t da, uint64_t db, int scale_d) {
  asm volatile(
      "{\n\t.reg .pred p;\n\tsetp.ne.b32 p, %130, 0;\n\t"
      "wgmma.mma_async.sync.aligned.m64n256k16.f32.bf16.bf16 "
      "{%0, %1, %2, %3, %4, %5, %6, %7, %8, %9, %10, %11, %12, %13, %14, %15, "
      "%16, %17, %18, %19, %20, %21, %22, %23, %24, %25, %26, %27, %28, %29, %30, %31, "
      "%32, %33, %34, %35, %36, %37, %38, %39, %40, %41, %42, %43, %44, %45, %46, %47, "
      "%48, %49, %50, %51, %52, %53, %54, %55, %56, %57, %58, %59, %60, %61, %62, %63, "
      "%64, %65, %66, %67, %68, %69, %70, %71, %72, %73, %74, %75, %76, %77, %78, %79, "
      "%80, %81, %82, %83, %84, %85, %86, %87, %88, %89, %90, %91, %92, %93, %94, %95, "
      "%96, %97, %98, %99, %100, %101, %102, %103, %104, %105, %106, %107, %108, %109, %110, %111, "
      "%112, %113, %114, %115, %116, %117, %118, %119, %120, %121, %122, %123, %124, %125, %126, %127}, "
      "%128, %129, p, 1, 1, 1, 0;\n\t}"
      : ACC32(0), ACC32(32), ACC32(64), ACC32(96)
      : "l"(da), "l"(db), "r"(scale_d));
}

__host__ __device__ constexpr int lead_f(int j) { return j + 1 + (j >= STAG0) + (j >= STAG1); }
__host__ __device__ constexpr bool lead_is(int k) {
  for (int j = 0; j < 12; j++) if (lead_f(j) == k) return k <= 11;
  return false;
}
__device__ __forceinline__ float gelu_half(float hy) {
  const float c1 = 2.0f * 0.7978845608028654f;
  const float c3 = 8.0f * 0.7978845608028654f * 0.044715f;
  float u = hy * fmaf(hy * hy, c3, c1);
  float t;
  asm("tanh.approx.f32 %0, %1;" : "=f"(t) : "f"(u));
  return fmaf(hy, t, hy);
}
__device__ __forceinline__ uint32_t pack_bf16(float lo, float hi) {
  uint32_t r;
  asm("cvt.rn.bf16x2.f32 %0, %1, %2;" : "=r"(r) : "f"(hi), "f"(lo));
  return r;
}

__global__ void __launch_bounds__(kThreads, 1)
conv_stem_kernel(const __grid_constant__ CUtensorMap tmX256, const __grid_constant__ CUtensorMap tmX1,
                 const __grid_constant__ CUtensorMap tmW, const __grid_constant__ CUtensorMap tmO,
                 const __nv_bfloat16* __restrict__ gamma, const __nv_bfloat16* __restrict__ beta) {
  extern __shared__ __align__(1024) uint8_t smem[];
  const uint32_t sb = smem_u32(smem);
  const uint32_t barXF = sb + kOffBar, barXE = barXF + 8 * kXSlots;
  const uint32_t barWF = barXE + 8 * kXSlots, barWE = barWF + 8 * kWStages;

  const int warp = threadIdx.x >> 5, lane = threadIdx.x & 31;
  const int h = blockIdx.x & 1;
  const int tile_g = blockIdx.x >> 1;
  const int b = tile_g / kTilesPerBatch, tile = tile_g % kTilesPerBatch;
  const int l0 = tile * 256;

  const unsigned cstart = (unsigned)clock();
  TSTAMP(0);
  auto loadW = [&](int kb) {
    const int s = kb % kWStages, c = kb / 3, j = kb % 3;
    const int tap = (j == 0) ? 0 : (j == 1 ? 2 : 1);
    const uint32_t bar = barWF + 8 * s;
    if (kb >= kWStages) mbar_wait(barWE + 8 * s, ((kb / kWStages) - 1) & 1);
    mbar_expect_tx(bar, kWStage);
    tma_load3(sb + kOffW + s * kWStage, &tmW, 0, tap * 256 + c * 64, h * 2, bar);
    CSTAMP(kb);
  };
  auto loadX = [&](int c, int odd) {
    const int s = (2 * c + odd) % kXSlots;
    const uint32_t dst = sb + s * kXSlot, bar = barXF + 8 * s;
    if (c >= 2) mbar_wait(barXE + 8 * s, 0);
    mbar_expect_tx(bar, odd ? 32768 : 32896);
    tma_load3(dst, &tmX256, odd * 256 + c * 64, l0, b, bar);
    if (!odd) tma_load3(dst + 32768, &tmX1, c * 64, l0 + 256, b, bar);
    CSTAMP(12 + 2 * c + odd);
  };

  if (warp == 8 && lane == 0) {
    for (int i = 0; i < kXSlots; i++) { mbar_init(barXF + 8 * i, 1); mbar_init(barXE + 8 * i, 2); }
    for (int i = 0; i < kWStages; i++) { mbar_init(barWF + 8 * i, 1); mbar_init(barWE + 8 * i, 2); }
    asm volatile("fence.mbarrier_init.release.cluster;" ::: "memory");
    asm volatile("fence.proxy.async.shared::cta;" ::: "memory");
    if (sb & 1023) __trap();
    CSTAMP(20);
    loadX(0, 0); loadW(0); loadW(1);
  }
  __syncthreads();
  TSTAMP(1);

  const int wg = (warp >> 2) & 1, wq = warp & 3;
  const bool elect = (threadIdx.x & 127) == 0;
  const int grp = h * 8 + wg * 4 + wq;
  const int ch0 = grp * 16 + (lane >> 2);
  float d[128];
  unsigned epoch = 0;
  float g0 = 0.f, g1 = 0.f, be0 = 0.f, be1 = 0.f;

  if (warp == 8) {
    if (lane == 0) {
      while ((unsigned)clock() - cstart < P1) {}
      loadX(0, 1); loadW(2);
      while ((unsigned)clock() - cstart < P2) {}
      loadX(1, 0); loadW(3); loadW(4);
      while ((unsigned)clock() - cstart < P3) {}
      loadX(1, 1);
      loadW(5); loadX(2, 0); loadW(6); loadX(2, 1); loadW(7); loadW(8);
      loadX(3, 0); loadW(9); loadX(3, 1); loadW(10); loadW(11);
    }
    return;
  }
  {
    asm volatile("ld.relaxed.gpu.global.u32 %0, [%1];" : "=r"(epoch) : "l"(&g_sync.epoch[b][grp]) : "memory");
    g0 = __bfloat162float(gamma[ch0]); g1 = __bfloat162float(gamma[ch0 + 8]);
    be0 = __bfloat162float(beta[ch0]); be1 = __bfloat162float(beta[ch0 + 8]);
#pragma unroll
    for (int kb = 0; kb < 12; kb++) {
      const int c = kb / 3, j = kb % 3, s = kb % kWStages;
      const int xs = (2 * c + (j == 2)) % kXSlots;
      auto release = [&](int pk) {
        const int pc = pk / 3, pj = pk % 3;
        if (elect) {
          if (pj != 0 && pc < 2) mbar_arrive(barXE + 8 * ((2 * pc + (pj == 2)) % kXSlots));
          if (pk + kWStages < 12) mbar_arrive(barWE + 8 * (pk % kWStages));
        }
      };
      if (wg == 1 && kb > 0 && lead_f(kb) <= 11) {
        asm volatile("wgmma.wait_group.sync.aligned 0;" ::: "memory");
        release(kb - 1);
      }
      if (j != 1) mbar_wait(barXF + 8 * xs, (c >> 1) & 1);
      if (kb == 0) TSTAMP(2);
      mbar_wait(barWF + 8 * s, (kb / kWStages) & 1);
      if (kb == 0) TSTAMP(3);
      if (kb == 3) TSTAMP(4);
      if (kb == 6) TSTAMP(5);
      if (kb == 9) TSTAMP(6);
      if (wg == 1 && lead_f(kb) <= 11) asm volatile("bar.sync 3, 256;" ::: "memory");
      if (wg == 0 && kb >= 1 && lead_is(kb - 1)) asm volatile("bar.sync 4, 256;" ::: "memory");
      const uint64_t da = make_desc(sb + kOffW + s * kWStage + wg * 8192);
      const uint64_t db = make_desc(sb + xs * kXSlot + (j == 1 ? 128 : 0));
      asm volatile("wgmma.fence.sync.aligned;" ::: "memory");
#pragma unroll
      for (int kk = 0; kk < 4; kk++)
        wgmma_m64n256k16(d, da + kk * (2048 >> 4), db + kk * (32 >> 4), (kb | kk) != 0);
      asm volatile("wgmma.commit_group.sync.aligned;" ::: "memory");
      if (wg == 0 && lead_is(kb)) asm volatile("bar.arrive 3, 256;" ::: "memory");
      if (wg == 1 && lead_f(kb) <= 10) asm volatile("bar.arrive 4, 256;" ::: "memory");
      if (kb > 0) {
        if (wg == 0 || lead_f(kb) > 11) {
          asm volatile("wgmma.wait_group.sync.aligned 1;" ::: "memory");
          release(kb - 1);
        }
      }
    }
    asm volatile("wgmma.wait_group.sync.aligned 0;" ::: "memory");
#pragma unroll
    for (int i = 0; i < 128; i++) asm volatile("" : "+f"(d[i])::"memory");
    if (tile == 0 && lane < 16) g_sync.stats[(epoch & 1) ^ 1][b][grp * 16 + lane] = make_float4(0.f, 0.f, 0.f, 0.f);
    if (tile == kTilesPerBatch - 1 && (lane & 3) == 3) { d[29] = 0.f; d[31] = 0.f; }
  }
  TSTAMP(7); TSTAMPB(12);

  float s0 = 0.f, s1 = 0.f, q0 = 0.f, q1 = 0.f, s0b = 0.f, s1b = 0.f, q0b = 0.f, q1b = 0.f;
#pragma unroll
  for (int i = 0; i < 32; i++) {
    s0 += d[4 * i]; s0b += d[4 * i + 1]; s1 += d[4 * i + 2]; s1b += d[4 * i + 3];
    q0 = fmaf(d[4 * i], d[4 * i], q0); q0b = fmaf(d[4 * i + 1], d[4 * i + 1], q0b);
    q1 = fmaf(d[4 * i + 2], d[4 * i + 2], q1); q1b = fmaf(d[4 * i + 3], d[4 * i + 3], q1b);
  }
  s0 += s0b; s1 += s1b; q0 += q0b; q1 += q1b;
  const bool hi = lane & 2;
  float s = (hi ? s1 : s0) + __shfl_xor_sync(~0u, hi ? s0 : s1, 2);
  float q = (hi ? q1 : q0) + __shfl_xor_sync(~0u, hi ? q0 : q1, 2);
  s += __shfl_xor_sync(~0u, s, 1);
  q += __shfl_xor_sync(~0u, q, 1);
  float4* st = &g_sync.stats[epoch & 1][b][ch0 + (hi ? 8 : 0)];
  float4 v = make_float4(0.f, 0.f, 0.f, 0.f);
  {
    uint32_t it = 0;
    if (!(lane & 1))
      asm volatile("red.relaxed.gpu.global.add.v4.f32 [%0], {%1, %2, %3, %4};"
                   ::"l"(st), "f"(s), "f"(q), "f"(1.0f), "f"(0.0f) : "memory");
    TSTAMP(8);
    do {
      asm volatile("ld.relaxed.gpu.global.v4.f32 {%0, %1, %2, %3}, [%4];"
                   : "=f"(v.x), "=f"(v.y), "=f"(v.z), "=f"(v.w) : "l"(st) : "memory");
      if (++it > kSpinLimit) __trap();
    } while (__any_sync(~0u, v.z < (float)kTilesPerBatch));
    if (tile == 0 && lane == 0) g_sync.epoch[b][grp] = epoch + 1;
  }
  TSTAMP(9); TSTAMPB(13);

  const float mean = v.x * (1.0f / kL);
  const float var = fmaxf(fmaf(-mean, mean, v.y * (1.0f / kL)), 0.f);
  const float rstd = rsqrtf(var + 1e-5f);
  const float mean_o = __shfl_xor_sync(~0u, mean, 2), rstd_o = __shfl_xor_sync(~0u, rstd, 2);
  const float a0 = 0.5f * g0 * (hi ? rstd_o : rstd), a1 = 0.5f * g1 * (hi ? rstd : rstd_o);
  const float b0 = fmaf(-(hi ? mean_o : mean), a0, 0.5f * be0), b1 = fmaf(-(hi ? mean : mean_o), a1, 0.5f * be1);

  const int mrow = lane & 7, mat = lane >> 3;
  const uint32_t chunk16 = (uint32_t)((wq * 2 + (mat & 1)) ^ mrow) << 4;
#pragma unroll
  for (int i = 0; i < 4; i++) {
    const uint32_t stage = sb + kOffW + i * kWStage + wg * 8192;
#pragma unroll
    for (int jj = 0; jj < 4; jj++) {
      const int j = i * 8 + jj * 2;
      const uint32_t r0 = pack_bf16(gelu_half(fmaf(d[4 * j], a0, b0)), gelu_half(fmaf(d[4 * j + 1], a0, b0)));
      const uint32_t r1 = pack_bf16(gelu_half(fmaf(d[4 * j + 2], a1, b1)), gelu_half(fmaf(d[4 * j + 3], a1, b1)));
      const uint32_t r2 = pack_bf16(gelu_half(fmaf(d[4 * j + 4], a0, b0)), gelu_half(fmaf(d[4 * j + 5], a0, b0)));
      const uint32_t r3 = pack_bf16(gelu_half(fmaf(d[4 * j + 6], a1, b1)), gelu_half(fmaf(d[4 * j + 7], a1, b1)));
      const uint32_t row = jj * 16 + (mat >> 1) * 8 + mrow;
      const uint32_t addr = stage + row * 128 + chunk16;
      asm volatile("stmatrix.sync.aligned.m8n8.x4.trans.shared.b16 [%0], {%1, %2, %3, %4};"
                   ::"r"(addr), "r"(r0), "r"(r1), "r"(r2), "r"(r3) : "memory");
    }
    if ((i + 1) % (4 / NCHUNK) == 0) {
      asm volatile("fence.proxy.async.shared::cta;" ::: "memory");
      asm volatile("bar.sync %0, 128;" ::"r"(1 + wg) : "memory");
      if (elect) {
#pragma unroll
        for (int ii = i + 1 - 4 / NCHUNK; ii <= i; ii++)
          if (l0 + ii * 64 < kL)
            tma_store3(&tmO, sb + kOffW + ii * kWStage + wg * 8192, h * 128 + wg * 64, l0 + ii * 64, b);
        asm volatile("cp.async.bulk.commit_group;" ::: "memory");
      }
    }
  }
  TSTAMP(10); TSTAMPB(14);
  if (elect) asm volatile("cp.async.bulk.wait_group.read 0;" ::: "memory");
  TSTAMP(11); TSTAMPB(15);
}

typedef CUresult (*EncodeFn)(CUtensorMap*, CUtensorMapDataType, cuuint32_t, void*, const cuuint64_t*,
                             const cuuint64_t*, const cuuint32_t*, const cuuint32_t*, CUtensorMapInterleave,
                             CUtensorMapSwizzle, CUtensorMapL2promotion, CUtensorMapFloatOOBfill);

void encode(EncodeFn fn, CUtensorMap* tm, const void* ptr, int rank, const cuuint64_t* dims,
            const cuuint64_t* strides, const cuuint32_t* box, CUtensorMapL2promotion promo) {
  const cuuint32_t es[3] = {1, 1, 1};
  fn(tm, CU_TENSOR_MAP_DATA_TYPE_BFLOAT16, rank, const_cast<void*>(ptr), dims, strides, box, es,
     CU_TENSOR_MAP_INTERLEAVE_NONE, CU_TENSOR_MAP_SWIZZLE_128B, promo, CU_TENSOR_MAP_FLOAT_OOB_FILL_NONE);
}

}

extern "C" void kernel_launch(void* const* d_in, const int* in_sizes, int n_in, void* d_out, int out_size) {
  static EncodeFn fn = nullptr;
  static CUtensorMap tmX256, tmX1, tmW, tmO;
  static const void* cached[3] = {nullptr, nullptr, nullptr};
  if (!fn) {
    cudaDriverEntryPointQueryResult qr;
    void* p = nullptr;
    cudaGetDriverEntryPoint("cuTensorMapEncodeTiled", &p, cudaEnableDefault, &qr);
    fn = (EncodeFn)p;
    cudaFuncSetAttribute(conv_stem_kernel, cudaFuncAttributeMaxDynamicSharedMemorySize, kSmemBytes);
  }
  if (cached[0] != d_in[0] || cached[1] != d_in[1] || cached[2] != d_out) {
    cached[0] = d_in[0]; cached[1] = d_in[1]; cached[2] = d_out;
    const cuuint64_t xd[3] = {512, kT / 2, 2}, xs[2] = {1024, (cuuint64_t)kT * kD * 2};
    const cuuint32_t b256[3] = {64, 256, 1}, b1[3] = {64, 1, 1};
    encode(fn, &tmX256, d_in[0], 3, xd, xs, b256, CU_TENSOR_MAP_L2_PROMOTION_L2_128B);
    encode(fn, &tmX1, d_in[0], 3, xd, xs, b1, CU_TENSOR_MAP_L2_PROMOTION_L2_128B);
    const cuuint64_t wd[3] = {64, 768, 4}, ws[2] = {512, 128};
    const cuuint32_t wb[3] = {64, 64, 2};
    encode(fn, &tmW, d_in[1], 3, wd, ws, wb, CU_TENSOR_MAP_L2_PROMOTION_L2_128B);
    const cuuint64_t od[3] = {256, kL, 2}, os[2] = {512, (cuuint64_t)kL * kD * 2};
    const cuuint32_t ob[3] = {64, 64, 1};
    encode(fn, &tmO, d_out, 3, od, os, ob, CU_TENSOR_MAP_L2_PROMOTION_NONE);
  }
  conv_stem_kernel<<<128, kThreads, kSmemBytes, cudaStreamPerThread>>>(
      tmX256, tmX1, tmW, tmO, (const __nv_bfloat16*)d_in[2], (const __nv_bfloat16*)d_in[3]);
}
```

```cpp
#include <cuda_runtime.h>
#include <cuda_bf16.h>
#include <cuda.h>
#include <stdint.h>

#define EVICT 1
#define NCHUNK 4
#define STAG0 7
#define STAG1 8
#define P1 2400u
#define P2 3600u
#define P3 5200u

namespace {

constexpr int kT = 16000, kD = 256, kL = 7999;
constexpr int kTilesPerBatch = 32;
constexpr int kXSlot = 33792;
constexpr int kXSlots = 4;
constexpr int kWStage = 16384;
constexpr int kWStages = 5;
constexpr int kOffW = kXSlots * kXSlot;
constexpr int kOffBar = kOffW + kWStages * kWStage;
constexpr int kSmemBytes = kOffBar + 256;
constexpr int kThreads = 288;
constexpr uint32_t kSpinLimit = 1u << 22;

struct Sync {
  float4 stats[2][2][256];
  unsigned epoch[2][16];
};
__device__ Sync g_sync;
#define TSTAMP(k)
#define TSTAMPB(k)
#define CSTAMP(k)

__device__ __forceinline__ uint32_t smem_u32(const void* p) { return (uint32_t)__cvta_generic_to_shared(p); }
__device__ __forceinline__ void mbar_init(uint32_t bar, uint32_t cnt) {
  asm volatile("mbarrier.init.shared::cta.b64 [%0], %1;" ::"r"(bar), "r"(cnt) : "memory");
}
__device__ __forceinline__ void mbar_expect_tx(uint32_t bar, uint32_t bytes) {
  asm volatile("mbarrier.arrive.expect_tx.shared::cta.b64 _, [%0], %1;" ::"r"(bar), "r"(bytes) : "memory");
}
__device__ __forceinline__ void mbar_wait(uint32_t bar, uint32_t parity) {
  uint32_t done, it = 0;
  do {
    asm volatile(
        "{\n\t.reg .pred p;\n\t"
        "mbarrier.try_wait.parity.shared::cta.b64 p, [%1], %2;\n\t"
        "selp.u32 %0, 1, 0, p;\n\t}"
        : "=r"(done) : "r"(bar), "r"(parity) : "memory");
    if (++it > kSpinLimit) __trap();
  } while (!done);
}
__device__ __forceinline__ void mbar_arrive(uint32_t bar) {
  asm volatile("mbarrier.arrive.shared::cta.b64 _, [%0];" ::"r"(bar) : "memory");
}
__device__ __forceinline__ void tma_load3(uint32_t dst, const CUtensorMap* tm, int c0, int c1, int c2, uint32_t bar) {
  asm volatile(
      "cp.async.bulk.tensor.3d.shared::cluster.global.mbarrier::complete_tx::bytes "
      "[%0], [%1, {%3, %4, %5}], [%2];"
      ::"r"(dst), "l"(tm), "r"(bar), "r"(c0), "r"(c1), "r"(c2) : "memory");
}
__device__ __forceinline__ void tma_store3(const CUtensorMap* tm, uint32_t src, int c0, int c1, int c2) {
  uint64_t pol;
  asm volatile("createpolicy.fractional.L2::evict_first.b64 %0, 1.0;" : "=l"(pol));
  asm volatile("cp.async.bulk.tensor.3d.global.shared::cta.bulk_group.L2::cache_hint [%0, {%2, %3, %4}], [%1], %5;"
               ::"l"(tm), "r"(src), "r"(c0), "r"(c1), "r"(c2), "l"(pol) : "memory");
}
__device__ __forceinline__ uint64_t make_desc(uint32_t addr) {
  return (uint64_t)((addr & 0x3FFFF) >> 4) | ((uint64_t)64 << 16) | ((uint64_t)64 << 32) | ((uint64_t)1 << 62);
}

#define ACC8(o) "+f"(d[o]), "+f"(d[o + 1]), "+f"(d[o + 2]), "+f"(d[o + 3]), "+f"(d[o + 4]), "+f"(d[o + 5]), "+f"(d[o + 6]), "+f"(d[o + 7])
#define ACC32(o) ACC8(o), ACC8(o + 8), ACC8(o + 16), ACC8(o + 24)
__device__ __forceinline__ void wgmma_m64n256k16(float (&d)[128], uint64_t da, uint64_t db, int scale_d) {
  asm volatile(
      "{\n\t.reg .pred p;\n\tsetp.ne.b32 p, %130, 0;\n\t"
      "wgmma.mma_async.sync.aligned.m64n256k16.f32.bf16.bf16 "
      "{%0, %1, %2, %3, %4, %5, %6, %7, %8, %9, %10, %11, %12, %13, %14, %15, "
      "%16, %17, %18, %19, %20, %21, %22, %23, %24, %25, %26, %27, %28, %29, %30, %31, "
      "%32, %33, %34, %35, %36, %37, %38, %39, %40, %41, %42, %43, %44, %45, %46, %47, "
      "%48, %49, %50, %51, %52, %53, %54, %55, %56, %57, %58, %59, %60, %61, %62, %63, "
      "%64, %65, %66, %67, %68, %69, %70, %71, %72, %73, %74, %75, %76, %77, %78, %79, "
      "%80, %81, %82, %83, %84, %85, %86, %87, %88, %89, %90, %91, %92, %93, %94, %95, "
      "%96, %97, %98, %99, %100, %101, %102, %103, %104, %105, %106, %107, %108, %109, %110, %111, "
      "%112, %113, %114, %115, %116, %117, %118, %119, %120, %121, %122, %123, %124, %125, %126, %127}, "
      "%128, %129, p, 1, 1, 1, 0;\n\t}"
      : ACC32(0), ACC32(32), ACC32(64), ACC32(96)
      : "l"(da), "l"(db), "r"(scale_d));
}

__host__ __device__ constexpr int lead_f(int j) { return j + 1 + (j >= STAG0) + (j >= STAG1); }
__host__ __device__ constexpr bool lead_is(int k) {
  for (int j = 0; j < 12; j++) if (lead_f(j) == k) return k <= 11;
  return false;
}
__device__ __forceinline__ float gelu_half(float hy) {
  const float c1 = 2.0f * 0.7978845608028654f;
  const float c3 = 8.0f * 0.7978845608028654f * 0.044715f;
  float u = hy * fmaf(hy * hy, c3, c1);
  float t;
  asm("tanh.approx.f32 %0, %1;" : "=f"(t) : "f"(u));
  return fmaf(hy, t, hy);
}
__device__ __forceinline__ uint32_t pack_bf16(float lo, float hi) {
  uint32_t r;
  asm("cvt.rn.bf16x2.f32 %0, %1, %2;" : "=r"(r) : "f"(hi), "f"(lo));
  return r;
}

__global__ void __launch_bounds__(kThreads, 1)
conv_stem_kernel(const __grid_constant__ CUtensorMap tmX256, const __grid_constant__ CUtensorMap tmX1,
                 const __grid_constant__ CUtensorMap tmW, const __grid_constant__ CUtensorMap tmO,
                 const __nv_bfloat16* __restrict__ gamma, const __nv_bfloat16* __restrict__ beta) {
  extern __shared__ __align__(1024) uint8_t smem[];
  const uint32_t sb = smem_u32(smem);
  const uint32_t barXF = sb + kOffBar, barXE = barXF + 8 * kXSlots;
  const uint32_t barWF = barXE + 8 * kXSlots, barWE = barWF + 8 * kWStages;

  const int warp = threadIdx.x >> 5, lane = threadIdx.x & 31;
  const int h = blockIdx.x & 1;
  const int tile_g = blockIdx.x >> 1;
  const int b = tile_g / kTilesPerBatch, tile = tile_g % kTilesPerBatch;
  const int l0 = tile * 256;

  const unsigned cstart = (unsigned)clock();
  TSTAMP(0);
  auto loadW = [&](int kb) {
    const int s = kb % kWStages, c = kb / 3, j = kb % 3;
    const int tap = (j == 0) ? 0 : (j == 1 ? 2 : 1);
    const uint32_t bar = barWF + 8 * s;
    if (kb >= kWStages) mbar_wait(barWE + 8 * s, ((kb / kWStages) - 1) & 1);
    mbar_expect_tx(bar, kWStage);
    tma_load3(sb + kOffW + s * kWStage, &tmW, 0, tap * 256 + c * 64, h * 2, bar);
    CSTAMP(kb);
  };
  auto loadX = [&](int c, int odd) {
    const int s = (2 * c + odd) % kXSlots;
    const uint32_t dst = sb + s * kXSlot, bar = barXF + 8 * s;
    if (c >= 2) mbar_wait(barXE + 8 * s, 0);
    mbar_expect_tx(bar, odd ? 32768 : 32896);
    tma_load3(dst, &tmX256, odd * 256 + c * 64, l0, b, bar);
    if (!odd) tma_load3(dst + 32768, &tmX1, c * 64, l0 + 256, b, bar);
    CSTAMP(12 + 2 * c + odd);
  };

  if (warp == 8 && lane == 0) {
    for (int i = 0; i < kXSlots; i++) { mbar_init(barXF + 8 * i, 1); mbar_init(barXE + 8 * i, 2); }
    for (int i = 0; i < kWStages; i++) { mbar_init(barWF + 8 * i, 1); mbar_init(barWE + 8 * i, 2); }
    asm volatile("fence.mbarrier_init.release.cluster;" ::: "memory");
    asm volatile("fence.proxy.async.shared::cta;" ::: "memory");
    if (sb & 1023) __trap();
    CSTAMP(20);
    loadW(0); loadX(0, 0); loadW(1);
  }
  __syncthreads();
  TSTAMP(1);

  const int wg = (warp >> 2) & 1, wq = warp & 3;
  const bool elect = (threadIdx.x & 127) == 0;
  const int grp = h * 8 + wg * 4 + wq;
  const int ch0 = grp * 16 + (lane >> 2);
  float d[128];
  unsigned epoch = 0;
  float g0 = 0.f, g1 = 0.f, be0 = 0.f, be1 = 0.f;

  if (warp == 8) {
    if (lane == 0) {
      while ((unsigned)clock() - cstart < P1) {}
      loadX(0, 1); loadW(2);
      while ((unsigned)clock() - cstart < P2) {}
      loadX(1, 0); loadW(3); loadW(4);
      while ((unsigned)clock() - cstart < P3) {}
      loadX(1, 1);
      loadW(5); loadX(2, 0); loadW(6); loadX(2, 1); loadW(7); loadW(8);
      loadX(3, 0); loadW(9); loadX(3, 1); loadW(10); loadW(11);
    }
    return;
  }
  {
    asm volatile("ld.relaxed.gpu.global.u32 %0, [%1];" : "=r"(epoch) : "l"(&g_sync.epoch[b][grp]) : "memory");
    g0 = __bfloat162float(gamma[ch0]); g1 = __bfloat162float(gamma[ch0 + 8]);
    be0 = __bfloat162float(beta[ch0]); be1 = __bfloat162float(beta[ch0 + 8]);
#pragma unroll
    for (int kb = 0; kb < 12; kb++) {
      const int c = kb / 3, j = kb % 3, s = kb % kWStages;
      const int xs = (2 * c + (j == 2)) % kXSlots;
      auto release = [&](int pk) {
        const int pc = pk / 3, pj = pk % 3;
        if (elect) {
          if (pj != 0 && pc < 2) mbar_arrive(barXE + 8 * ((2 * pc + (pj == 2)) % kXSlots));
          if (pk + kWStages < 12) mbar_arrive(barWE + 8 * (pk % kWStages));
        }
      };
      if (wg == 1 && kb > 0 && lead_f(kb) <= 11) {
        asm volatile("wgmma.wait_group.sync.aligned 0;" ::: "memory");
        release(kb - 1);
      }
      if (j != 1) mbar_wait(barXF + 8 * xs, (c >> 1) & 1);
      if (kb == 0) TSTAMP(2);
      mbar_wait(barWF + 8 * s, (kb / kWStages) & 1);
      if (kb == 0) TSTAMP(3);
      if (kb == 3) TSTAMP(4);
      if (kb == 6) TSTAMP(5);
      if (kb == 9) TSTAMP(6);
      if (wg == 1 && lead_f(kb) <= 11) asm volatile("bar.sync 3, 256;" ::: "memory");
      if (wg == 0 && kb >= 1 && lead_is(kb - 1)) asm volatile("bar.sync 4, 256;" ::: "memory");
      const uint64_t da = make_desc(sb + kOffW + s * kWStage + wg * 8192);
      const uint64_t db = make_desc(sb + xs * kXSlot + (j == 1 ? 128 : 0));
      asm volatile("wgmma.fence.sync.aligned;" ::: "memory");
#pragma unroll
      for (int kk = 0; kk < 4; kk++)
        wgmma_m64n256k16(d, da + kk * (2048 >> 4), db + kk * (32 >> 4), (kb | kk) != 0);
      asm volatile("wgmma.commit_group.sync.aligned;" ::: "memory");
      if (wg == 0 && lead_is(kb)) asm volatile("bar.arrive 3, 256;" ::: "memory");
      if (wg == 1 && lead_f(kb) <= 10) asm volatile("bar.arrive 4, 256;" ::: "memory");
      if (kb > 0) {
        if (wg == 0 || lead_f(kb) > 11) {
          asm volatile("wgmma.wait_group.sync.aligned 1;" ::: "memory");
          release(kb - 1);
        }
      }
    }
    asm volatile("wgmma.wait_group.sync.aligned 0;" ::: "memory");
#pragma unroll
    for (int i = 0; i < 128; i++) asm volatile("" : "+f"(d[i])::"memory");
    if (tile == 0 && lane < 16) g_sync.stats[(epoch & 1) ^ 1][b][grp * 16 + lane] = make_float4(0.f, 0.f, 0.f, 0.f);
    if (tile == kTilesPerBatch - 1 && (lane & 3) == 3) { d[29] = 0.f; d[31] = 0.f; }
  }
  TSTAMP(7); TSTAMPB(12);

  float s0 = 0.f, s1 = 0.f, q0 = 0.f, q1 = 0.f, s0b = 0.f, s1b = 0.f, q0b = 0.f, q1b = 0.f;
#pragma unroll
  for (int i = 0; i < 32; i++) {
    s0 += d[4 * i]; s0b += d[4 * i + 1]; s1 += d[4 * i + 2]; s1b += d[4 * i + 3];
    q0 = fmaf(d[4 * i], d[4 * i], q0); q0b = fmaf(d[4 * i + 1], d[4 * i + 1], q0b);
    q1 = fmaf(d[4 * i + 2], d[4 * i + 2], q1); q1b = fmaf(d[4 * i + 3], d[4 * i + 3], q1b);
  }
  s0 += s0b; s1 += s1b; q0 += q0b; q1 += q1b;
  const bool hi = lane & 2;
  float s = (hi ? s1 : s0) + __shfl_xor_sync(~0u, hi ? s0 : s1, 2);
  float q = (hi ? q1 : q0) + __shfl_xor_sync(~0u, hi ? q0 : q1, 2);
  s += __shfl_xor_sync(~0u, s, 1);
  q += __shfl_xor_sync(~0u, q, 1);
  float4* st = &g_sync.stats[epoch & 1][b][ch0 + (hi ? 8 : 0)];
  float4 v = make_float4(0.f, 0.f, 0.f, 0.f);
  {
    uint32_t it = 0;
    if (!(lane & 1))
      asm volatile("red.relaxed.gpu.global.add.v4.f32 [%0], {%1, %2, %3, %4};"
                   ::"l"(st), "f"(s), "f"(q), "f"(1.0f), "f"(0.0f) : "memory");
    TSTAMP(8);
    do {
      asm volatile("ld.relaxed.gpu.global.v4.f32 {%0, %1, %2, %3}, [%4];"
                   : "=f"(v.x), "=f"(v.y), "=f"(v.z), "=f"(v.w) : "l"(st) : "memory");
      if (++it > kSpinLimit) __trap();
    } while (__any_sync(~0u, v.z < (float)kTilesPerBatch));
    if (tile == 0 && lane == 0) g_sync.epoch[b][grp] = epoch + 1;
  }
  TSTAMP(9); TSTAMPB(13);

  const float mean = v.x * (1.0f / kL);
  const float var = fmaxf(fmaf(-mean, mean, v.y * (1.0f / kL)), 0.f);
  const float rstd = rsqrtf(var + 1e-5f);
  const float mean_o = __shfl_xor_sync(~0u, mean, 2), rstd_o = __shfl_xor_sync(~0u, rstd, 2);
  const float a0 = 0.5f * g0 * (hi ? rstd_o : rstd), a1 = 0.5f * g1 * (hi ? rstd : rstd_o);
  const float b0 = fmaf(-(hi ? mean_o : mean), a0, 0.5f * be0), b1 = fmaf(-(hi ? mean : mean_o), a1, 0.5f * be1);

  const int mrow = lane & 7, mat = lane >> 3;
  const uint32_t chunk16 = (uint32_t)((wq * 2 + (mat & 1)) ^ mrow) << 4;
#pragma unroll
  for (int i = 0; i < 4; i++) {
    const uint32_t stage = sb + kOffW + i * kWStage + wg * 8192;
#pragma unroll
    for (int jj = 0; jj < 4; jj++) {
      const int j = i * 8 + jj * 2;
      const uint32_t r0 = pack_bf16(gelu_half(fmaf(d[4 * j], a0, b0)), gelu_half(fmaf(d[4 * j + 1], a0, b0)));
      const uint32_t r1 = pack_bf16(gelu_half(fmaf(d[4 * j + 2], a1, b1)), gelu_half(fmaf(d[4 * j + 3], a1, b1)));
      const uint32_t r2 = pack_bf16(gelu_half(fmaf(d[4 * j + 4], a0, b0)), gelu_half(fmaf(d[4 * j + 5], a0, b0)));
      const uint32_t r3 = pack_bf16(gelu_half(fmaf(d[4 * j + 6], a1, b1)), gelu_half(fmaf(d[4 * j + 7], a1, b1)));
      const uint32_t row = jj * 16 + (mat >> 1) * 8 + mrow;
      const uint32_t addr = stage + row * 128 + chunk16;
      asm volatile("stmatrix.sync.aligned.m8n8.x4.trans.shared.b16 [%0], {%1, %2, %3, %4};"
                   ::"r"(addr), "r"(r0), "r"(r1), "r"(r2), "r"(r3) : "memory");
    }
    if ((i + 1) % (4 / NCHUNK) == 0) {
      asm volatile("fence.proxy.async.shared::cta;" ::: "memory");
      asm volatile("bar.sync %0, 128;" ::"r"(1 + wg) : "memory");
      if (elect) {
#pragma unroll
        for (int ii = i + 1 - 4 / NCHUNK; ii <= i; ii++)
          if (l0 + ii * 64 < kL)
            tma_store3(&tmO, sb + kOffW + ii * kWStage + wg * 8192, h * 128 + wg * 64, l0 + ii * 64, b);
        asm volatile("cp.async.bulk.commit_group;" ::: "memory");
      }
    }
  }
  TSTAMP(10); TSTAMPB(14);
  if (elect) asm volatile("cp.async.bulk.wait_group.read 0;" ::: "memory");
  TSTAMP(11); TSTAMPB(15);
}

typedef CUresult (*EncodeFn)(CUtensorMap*, CUtensorMapDataType, cuuint32_t, void*, const cuuint64_t*,
                             const cuuint64_t*, const cuuint32_t*, const cuuint32_t*, CUtensorMapInterleave,
                             CUtensorMapSwizzle, CUtensorMapL2promotion, CUtensorMapFloatOOBfill);

void encode(EncodeFn fn, CUtensorMap* tm, const void* ptr, int rank, const cuuint64_t* dims,
            const cuuint64_t* strides, const cuuint32_t* box, CUtensorMapL2promotion promo) {
  const cuuint32_t es[3] = {1, 1, 1};
  fn(tm, CU_TENSOR_MAP_DATA_TYPE_BFLOAT16, rank, const_cast<void*>(ptr), dims, strides, box, es,
     CU_TENSOR_MAP_INTERLEAVE_NONE, CU_TENSOR_MAP_SWIZZLE_128B, promo, CU_TENSOR_MAP_FLOAT_OOB_FILL_NONE);
}

}

extern "C" void kernel_launch(void* const* d_in, const int* in_sizes, int n_in, void* d_out, int out_size) {
  static EncodeFn fn = nullptr;
  static CUtensorMap tmX256, tmX1, tmW, tmO;
  static const void* cached[3] = {nullptr, nullptr, nullptr};
  if (!fn) {
    cudaDriverEntryPointQueryResult qr;
    void* p = nullptr;
    cudaGetDriverEntryPoint("cuTensorMapEncodeTiled", &p, cudaEnableDefault, &qr);
    fn = (EncodeFn)p;
    cudaFuncSetAttribute(conv_stem_kernel, cudaFuncAttributeMaxDynamicSharedMemorySize, kSmemBytes);
  }
  if (cached[0] != d_in[0] || cached[1] != d_in[1] || cached[2] != d_out) {
    cached[0] = d_in[0]; cached[1] = d_in[1]; cached[2] = d_out;
    const cuuint64_t xd[3] = {512, kT / 2, 2}, xs[2] = {1024, (cuuint64_t)kT * kD * 2};
    const cuuint32_t b256[3] = {64, 256, 1}, b1[3] = {64, 1, 1};
    encode(fn, &tmX256, d_in[0], 3, xd, xs, b256, CU_TENSOR_MAP_L2_PROMOTION_L2_128B);
    encode(fn, &tmX1, d_in[0], 3, xd, xs, b1, CU_TENSOR_MAP_L2_PROMOTION_L2_128B);
    const cuuint64_t wd[3] = {64, 768, 4}, ws[2] = {512, 128};
    const cuuint32_t wb[3] = {64, 64, 2};
    encode(fn, &tmW, d_in[1], 3, wd, ws, wb, CU_TENSOR_MAP_L2_PROMOTION_L2_128B);
    const cuuint64_t od[3] = {256, kL, 2}, os[2] = {512, (cuuint64_t)kL * kD * 2};
    const cuuint32_t ob[3] = {64, 64, 1};
    encode(fn, &tmO, d_out, 3, od, os, ob, CU_TENSOR_MAP_L2_PROMOTION_NONE);
  }
  conv_stem_kernel<<<128, kThreads, kSmemBytes, cudaStreamPerThread>>>(
      tmX256, tmX1, tmW, tmO, (const __nv_bfloat16*)d_in[2], (const __nv_bfloat16*)d_in[3]);
}
```
